```python
import torch

def _softmax(x, axis=-1):
    return torch.softmax(x, dim=axis)
def _gelu(x):
    return torch.nn.functional.gelu(x, approximate="tanh")
def _silu(x):
    return torch.nn.functional.silu(x)
def _sigmoid(x):
    return torch.sigmoid(x)
def _layernorm(x, axis=-1, eps=1e-5):
    m = x.mean(dim=axis, keepdim=True)
    v = x.var(dim=axis, keepdim=True, unbiased=False)
    return (x - m) / torch.sqrt(v + eps)
def _scatter_add(tgt, idx, src, axis=0):
    return tgt.clone().index_add_(axis, idx, src)
def _segment_sum(src, seg, n):
    out = torch.zeros((n,) + src.shape[1:], dtype=src.dtype)
    return out.index_add_(0, seg, src)
def _pad(x, pw):
    flat = tuple(v for pair in reversed(pw) for v in pair)
    return torch.nn.functional.pad(x, flat)

kernel_name = 'concat_heads__gqa_block_cached__mha_block_cached__near_ridge'

def setup_inputs():

    _w = (lambda a: (lambda t: t.to(torch.bfloat16) if t.is_floating_point() else t)(torch.as_tensor(a)))
    def _A_setup():
        B, Sq, D = 32, 48, 512
        Hq, Hkv, Sk, Dh = 32, 8, 512, 128
        assert Hq % Hkv == 0, (Hq, Hkv)
        return {
            "x": _w((lambda *s: torch.randn(*s, dtype=torch.bfloat16) * 0.8)(B, Sq, D)),
            "k_cache": _w((lambda *s: torch.randn(*s, dtype=torch.bfloat16) * 0.8)(B, Hkv, Sk, Dh)),
            "v_cache": _w((lambda *s: torch.randn(*s, dtype=torch.bfloat16) * 0.05)(B, Hkv, Sk, Dh)),
            "wq": _w((lambda *s: torch.randn(*s, dtype=torch.bfloat16) * 0.8)(D, Hq * Dh) * (D ** -0.5)),
            "wo": _w((lambda *s: torch.randn(*s, dtype=torch.bfloat16) * 0.05)(Hq * Dh, D) * ((Hq * Dh) ** -0.5)),
        }
    _A_in = _A_setup()

    def _B_setup():
        B, Sq, D = 32, 48, 512
        H, Sk, Dh = 32, 512, 128
        return {
            "x": _w((lambda *s: torch.randn(*s, dtype=torch.bfloat16) * 0.8)(B, Sq, D)),
            "k_cache": _w((lambda *s: torch.randn(*s, dtype=torch.bfloat16) * 0.8)(B, H, Sk, Dh)),
            "v_cache": _w((lambda *s: torch.randn(*s, dtype=torch.bfloat16) * 0.05)(B, H, Sk, Dh)),
            "wq": _w((lambda *s: torch.randn(*s, dtype=torch.bfloat16) * 0.8)(D, H * Dh) * (D ** -0.5)),
            "wo": _w((lambda *s: torch.randn(*s, dtype=torch.bfloat16) * 0.05)(H * Dh, D) * ((H * Dh) ** -0.5)),
        }
    _B_in = _B_setup()

    return {
        "A_x": _A_in["x"],
        "A_k_cache": _A_in["k_cache"],
        "A_v_cache": _A_in["v_cache"],
        "A_wq": _A_in["wq"],
        "A_wo": _A_in["wo"],
        "B_x": _B_in["x"],
        "B_k_cache": _B_in["k_cache"],
        "B_v_cache": _B_in["v_cache"],
        "B_wq": _B_in["wq"],
        "B_wo": _B_in["wo"],
    }

def reference(A_x, A_k_cache, A_v_cache, A_wq, A_wo, B_x, B_k_cache, B_v_cache, B_wq, B_wo):
    def _A_ref(x, k_cache, v_cache, wq, wo):
        B, Sq, D = x.shape
        Hq, Dh = 32, 128
        Hkv = k_cache.shape[1]
        rep = Hq // Hkv
        q = (lambda x, *d: x.permute(*d))((x @ wq).reshape(B, Sq, Hq, Dh), 0, 2, 1, 3)
        k = (lambda x, n, axis: torch.repeat_interleave(x, n, dim=axis))(k_cache, rep, axis=1)
        v = (lambda x, n, axis: torch.repeat_interleave(x, n, dim=axis))(v_cache, rep, axis=1)
        scores = torch.einsum("bhqd,bhkd->bhqk", q, k) * (Dh ** -0.5)
        p = _softmax(scores, axis=-1)
        o = torch.einsum("bhqk,bhkd->bhqd", p, v)
        return (lambda x, *d: x.permute(*d))(o, 0, 2, 1, 3).reshape(B, Sq, Hq * Dh) @ wo

    def _B_ref(x, k_cache, v_cache, wq, wo):
        B, Sq, D = x.shape
        H, Dh = 32, 128
        q = (lambda x, *d: x.permute(*d))((x @ wq).reshape(B, Sq, H, Dh), 0, 2, 1, 3)
        scores = torch.einsum("bhqd,bhkd->bhqk", q, k_cache) * (Dh ** -0.5)
        p = _softmax(scores, axis=-1)
        o = torch.einsum("bhqk,bhkd->bhqd", p, v_cache)
        return (lambda x, *d: x.permute(*d))(o, 0, 2, 1, 3).reshape(B, Sq, H * Dh) @ wo

    a = _A_ref(A_x, A_k_cache, A_v_cache, A_wq, A_wo)
    b = _B_ref(B_x, B_k_cache, B_v_cache, B_wq, B_wo)
    return torch.concatenate([a, b], axis=-1)
```

```cpp
#include <cuda_runtime.h>
#include <cuda.h>
#include <cuda_bf16.h>
#include <stdint.h>

namespace {

constexpr int N_OP = 32;
#define N_QP_ 22
constexpr int N_QP = N_QP_;
constexpr int N_GEMM = N_OP + N_QP;
#define RING_A 12
#define RING_B 8
constexpr int RA = RING_A, RB = RING_B;
#define NB0_ 96
#define SPAN_ 960
constexpr int NB0 = NB0_ / 2;
constexpr int SPAN = SPAN_ / 2;
constexpr int N_ITEMS = 640;
#define REQ_T 6
#define PF0 0
#define SPLIT 4
#define BORDER 1
#define SENDX 1
#define HT 24
#define QLEAD 4
#define KV_CAP 2
#define CAP_TAIL 0
#define CAP_END 5
#define CAP_LO 160
#define CAP_OFF 0
#define CAP_MOD 4
#define CAP_NUM 3
#define H0_ 24
constexpr int H0 = H0_;
__host__ __device__ constexpr int wave1(int side) { return (N_GEMM / 2 + 1 - side) / 2; }
constexpr int XHP = 4;
constexpr int QPS = N_QP / 2;
static_assert(H0 >= 24 && H0 >= 32 - RB && N_QP >= 16 && N_QP % 2 == 0 && 2 * XHP + 4 <= RA, "hand-over assumes no ring reuse after H0");
constexpr int N_PAIRS = (RA + RB) * 16 * 3 + 1;
constexpr int N_PAGES = N_PAIRS * 8192 / (1 << 21) + 2;
constexpr uint32_t SIDE_BITS = (1u << 13) | (1u << 16) | (1u << 17) | (1u << 19);
constexpr int KV_SLOTS = 5;
constexpr int KVT = 32768;
constexpr int TILE = 16384;
constexpr int QBLK = 12288;
constexpr int GA_BYTES = 24576;
constexpr int GB_BYTES = 32768;
constexpr int SM_GB = 4 * GA_BYTES;
constexpr int SM_Q = KV_SLOTS * KVT;
constexpr int SM_BAR = 229376;
constexpr int SMEM_BYTES = SM_BAR + 1024 + 1024;
constexpr uint32_t INFO_DONE = 0xFFFFFFFFu;

struct alignas(64) Params {
  CUtensorMap kmap[2], vmap[2], xmap[2], wqmap[2], womap[2];
  CUtensorMap omap;
  CUtensorMap x1map, wq1map;
  uint8_t qorder[128];
  uint32_t boot[160];
  int n_qtiles;
};

struct Ctrs {
  unsigned cntQ[2 * 8 * 16];
  unsigned cntO[2 * 8 * 32];
  unsigned cntF[2 * 8 * 32];
  unsigned cntD[16];
  alignas(128) unsigned cntL[8 * 64];
  unsigned long long exits;
  struct alignas(8) Launch {
    unsigned item[2];
    unsigned ticket[2][3];
    unsigned phase;
    unsigned pad;
  } launch[2];
};
__device__ Ctrs g_ctr;
__device__ __align__(8192) uint4 g_qo[N_PAIRS * 512];
__device__ float4 g_dump[16 * 16 * 384];
__device__ __forceinline__ uint32_t qo_lo() {
  uint32_t lo;
  asm("cvt.u32.u64 %0, %1;" : "=r"(lo) : "l"(&g_qo[0]));
  return lo;
}
__device__ __forceinline__ uint32_t qo_pair(int p, int h, int b, int j) {
  return ((p ? RA + h % RB : h % RA) * 16 + (b & 15)) * 3 + j + 1;
}
__device__ __forceinline__ uint8_t* qo_block(int p, int h, int b, int j, uint32_t phase) {
  uint8_t* const base = reinterpret_cast<uint8_t*>(g_qo);
  uint8_t* const a = base + qo_pair(p, h, b, j) * 8192;
  const uint32_t page = (uint32_t)(((uintptr_t)a >> 21) - ((uintptr_t)base >> 21));
  return a + (((__popc((uint32_t)(uintptr_t)a & SIDE_BITS) ^ (phase >> page) ^ (b >> 4)) & 1) << 12);
}
#define TCK(idx)
#define TC(e)
#define TR(ch, idx, tag)

__device__ __forceinline__ uint32_t s2u(const void* p) { return (uint32_t)__cvta_generic_to_shared(p); }
__device__ __forceinline__ void mbar_init(uint32_t b, int c) {
  asm volatile("mbarrier.init.shared::cta.b64 [%0], %1;" ::"r"(b), "r"(c) : "memory");
}
__device__ __forceinline__ void mbar_expect(uint32_t b, int bytes) {
  asm volatile("mbarrier.arrive.expect_tx.shared::cta.b64 _, [%0], %1;" ::"r"(b), "r"(bytes) : "memory");
}
__device__ __forceinline__ void mbar_arrive(uint32_t b) {
  asm volatile("mbarrier.arrive.shared::cta.b64 _, [%0];" ::"r"(b) : "memory");
}
__device__ __forceinline__ void mbar_arrive_n(uint32_t b, uint32_t n) {
  asm volatile("mbarrier.arrive.shared::cta.b64 _, [%0], %1;" ::"r"(b), "r"(n) : "memory");
}
__device__ __forceinline__ void mbar_wait(uint32_t b, uint32_t ph) {
  asm volatile(
      "{\n.reg .pred p;\n.reg .u32 c;\n.reg .u64 z;\n"
      "mov.u32 c, 0;\nmov.u64 z, 0;\n"
      "WAIT_LOOP:\n"
      "mbarrier.try_wait.parity.shared::cta.b64 p, [%0], %1;\n"
      "@p bra WAIT_DONE;\n"
      "add.u32 c, c, 1;\n"
      "setp.gt.u32 p, c, 16777216;\n"
      "@p st.volatile.global.u32 [z], c;\n"
      "bra WAIT_LOOP;\n"
      "WAIT_DONE:\n}"
      ::"r"(b), "r"(ph) : "memory");
}
__device__ __forceinline__ void tma3(uint32_t dst, const CUtensorMap* m, uint32_t bar, int c0, int c1, int c2) {
  asm volatile("cp.async.bulk.tensor.3d.shared::cluster.global.mbarrier::complete_tx::bytes [%0], [%1, {%3,%4,%5}], [%2];"
               ::"r"(dst), "l"(m), "r"(bar), "r"(c0), "r"(c1), "r"(c2) : "memory");
}
__device__ __forceinline__ void tma3_hint(uint32_t dst, const CUtensorMap* m, uint32_t bar, int c0, int c1, int c2, uint64_t pol) {
  asm volatile("cp.async.bulk.tensor.3d.shared::cluster.global.mbarrier::complete_tx::bytes.L2::cache_hint [%0], [%1, {%3,%4,%5}], [%2], %6;"
               ::"r"(dst), "l"(m), "r"(bar), "r"(c0), "r"(c1), "r"(c2), "l"(pol) : "memory");
}
__device__ __forceinline__ void tma2(uint32_t dst, const CUtensorMap* m, uint32_t bar, int c0, int c1) {
  asm volatile("cp.async.bulk.tensor.2d.shared::cluster.global.mbarrier::complete_tx::bytes [%0], [%1, {%3,%4}], [%2];"
               ::"r"(dst), "l"(m), "r"(bar), "r"(c0), "r"(c1) : "memory");
}
__device__ __forceinline__ void bulk_g2s(uint32_t dst, const void* src, int bytes, uint32_t bar) {
  asm volatile("cp.async.bulk.shared::cluster.global.mbarrier::complete_tx::bytes [%0], [%1], %2, [%3];"
               ::"r"(dst), "l"(src), "r"(bytes), "r"(bar) : "memory");
}
__device__ __forceinline__ void bulk_g2s_hint(uint32_t dst, const void* src, int bytes, uint32_t bar, uint64_t pol) {
  asm volatile("cp.async.bulk.shared::cluster.global.mbarrier::complete_tx::bytes.L2::cache_hint [%0], [%1], %2, [%3], %4;"
               ::"r"(dst), "l"(src), "r"(bytes), "r"(bar), "l"(pol) : "memory");
}
__device__ __forceinline__ uint64_t pol_ef() {
  uint64_t pol;
  asm volatile("createpolicy.fractional.L2::evict_first.b64 %0, 1.0;" : "=l"(pol));
  return pol;
}
#define bulk_g2s(d, s, b, r) bulk_g2s_hint(d, s, b, r, pol_ef())
__device__ __forceinline__ void red_relaxed(unsigned* p, unsigned n) {
  asm volatile("red.relaxed.gpu.global.add.u32 [%0], %1;" ::"l"(p), "r"(n) : "memory");
}
__device__ __forceinline__ bool elect_one() {
  uint32_t pred;
  asm volatile("{\n.reg .pred p;\nelect.sync _|p, 0xffffffff;\nselp.u32 %0, 1, 0, p;\n}" : "=r"(pred));
  return pred;
}
__device__ __forceinline__ void fence_gpu() { asm volatile("fence.release.gpu;" ::: "memory"); }
__device__ __forceinline__ bool mbar_test(uint32_t b, uint32_t ph) {
  uint32_t ok;
  asm volatile("{\n.reg .pred p;\nmbarrier.test_wait.parity.shared::cta.b64 p, [%1], %2;\nselp.u32 %0, 1, 0, p;\n}"
               : "=r"(ok) : "r"(b), "r"(ph) : "memory");
  return ok;
}
__device__ __forceinline__ void bar_sync(int id, int n) { asm volatile("bar.sync %0, %1;" ::"r"(id), "r"(n) : "memory"); }
__device__ __forceinline__ void bar_arrive(int id, int n) { asm volatile("bar.arrive %0, %1;" ::"r"(id), "r"(n) : "memory"); }
__device__ __forceinline__ void sts32(uint32_t a, uint32_t v) { asm volatile("st.shared.u32 [%0], %1;" ::"r"(a), "r"(v) : "memory"); }
__device__ __forceinline__ uint32_t lds32(uint32_t a) {
  uint32_t v;
  asm volatile("ld.shared.u32 %0, [%1];" : "=r"(v) : "r"(a) : "memory");
  return v;
}
__device__ __forceinline__ void poll_ge(const unsigned* p, unsigned target, unsigned ns = 40) {
  asm volatile(
      "{\n.reg .pred p;\n.reg .u32 c, v;\n.reg .u64 z;\n"
      "mov.u32 c, 0;\nmov.u64 z, 0;\n"
      "POLL_LOOP:\n"
      "ld.acquire.gpu.global.u32 v, [%0];\n"
      "sub.u32 v, v, %1;\n"
      "setp.ge.s32 p, v, 0;\n"
      "@p bra POLL_DONE;\n"
      "add.u32 c, c, 1;\n"
      "setp.gt.u32 p, c, 4194304;\n"
      "@p st.volatile.global.u32 [z], c;\n"
      "nanosleep.u32 %2;\n"
      "bra POLL_LOOP;\n"
      "POLL_DONE:\n}"
      ::"l"(p), "r"(target), "r"(ns) : "memory");
}
__device__ __forceinline__ void fence_async_global() { asm volatile("fence.proxy.async.global;" ::: "memory"); }
__device__ __forceinline__ void wg_fence() { asm volatile("wgmma.fence.sync.aligned;" ::: "memory"); }
__device__ __forceinline__ void wg_commit() { asm volatile("wgmma.commit_group.sync.aligned;" ::: "memory"); }
template <int N> __device__ __forceinline__ void wg_wait() { asm volatile("wgmma.wait_group.sync.aligned %0;" ::"n"(N) : "memory"); }
template <int N> __device__ __forceinline__ void reg_fence(float (&d)[N]) {
#pragma unroll
  for (int i = 0; i < N; i++) asm volatile("" : "+f"(d[i])::"memory");
}
__device__ __forceinline__ uint32_t pack_bf16(float lo, float hi) {
  uint32_t r;
  asm("cvt.rn.bf16x2.f32 %0, %1, %2;" : "=r"(r) : "f"(hi), "f"(lo));
  return r;
}
__device__ __forceinline__ float ex2(float x) {
  float y;
  asm("ex2.approx.ftz.f32 %0, %1;" : "=f"(y) : "f"(x));
  return y;
}
__device__ __forceinline__ uint64_t mkdesc(uint32_t addr, uint32_t lbo, uint32_t sbo, uint32_t swz) {
  uint32_t lo = ((addr & 0x3FFFF) >> 4) | ((lbo >> 4) << 16);
  uint32_t hi = (sbo >> 4) | (swz << 30);
  return ((uint64_t)hi << 32) | lo;
}

__device__ __forceinline__ void wgmma_ss_n128_tb(float (&d)[64], uint64_t da, uint64_t db, int scale_d) {
  asm volatile("{\n.reg .pred p;\nsetp.ne.b32 p, %66, 0;\n"
    "wgmma.mma_async.sync.aligned.m64n128k16.f32.bf16.bf16 "
    "{%0, %1, %2, %3, %4, %5, %6, %7, %8, %9, %10, %11, %12, %13, %14, %15, %16, %17, %18, %19, %20, %21, %22, %23, %24, %25, %26, %27, %28, %29, %30, %31, %32, %33, %34, %35, %36, %37, %38, %39, %40, %41, %42, %43, %44, %45, %46, %47, %48, %49, %50, %51, %52, %53, %54, %55, %56, %57, %58, %59, %60, %61, %62, %63}, "
    "%64, %65, p, 1, 1, 0, 1;\n}\n"
    : "+f"(d[0]), "+f"(d[1]), "+f"(d[2]), "+f"(d[3]), "+f"(d[4]), "+f"(d[5]), "+f"(d[6]), "+f"(d[7]), "+f"(d[8]), "+f"(d[9]), "+f"(d[10]), "+f"(d[11]), "+f"(d[12]), "+f"(d[13]), "+f"(d[14]), "+f"(d[15]), "+f"(d[16]), "+f"(d[17]), "+f"(d[18]), "+f"(d[19]), "+f"(d[20]), "+f"(d[21]), "+f"(d[22]), "+f"(d[23]), "+f"(d[24]), "+f"(d[25]), "+f"(d[26]), "+f"(d[27]), "+f"(d[28]), "+f"(d[29]), "+f"(d[30]), "+f"(d[31]), "+f"(d[32]), "+f"(d[33]), "+f"(d[34]), "+f"(d[35]), "+f"(d[36]), "+f"(d[37]), "+f"(d[38]), "+f"(d[39]), "+f"(d[40]), "+f"(d[41]), "+f"(d[42]), "+f"(d[43]), "+f"(d[44]), "+f"(d[45]), "+f"(d[46]), "+f"(d[47]), "+f"(d[48]), "+f"(d[49]), "+f"(d[50]), "+f"(d[51]), "+f"(d[52]), "+f"(d[53]), "+f"(d[54]), "+f"(d[55]), "+f"(d[56]), "+f"(d[57]), "+f"(d[58]), "+f"(d[59]), "+f"(d[60]), "+f"(d[61]), "+f"(d[62]), "+f"(d[63])
    : "l"(da), "l"(db), "r"(scale_d));
}

__device__ __forceinline__ void wgmma_ss_n128(float (&d)[64], uint64_t da, uint64_t db, int scale_d) {
  asm volatile("{\n.reg .pred p;\nsetp.ne.b32 p, %66, 0;\n"
    "wgmma.mma_async.sync.aligned.m64n128k16.f32.bf16.bf16 "
    "{%0, %1, %2, %3, %4, %5, %6, %7, %8, %9, %10, %11, %12, %13, %14, %15, %16, %17, %18, %19, %20, %21, %22, %23, %24, %25, %26, %27, %28, %29, %30, %31, %32, %33, %34, %35, %36, %37, %38, %39, %40, %41, %42, %43, %44, %45, %46, %47, %48, %49, %50, %51, %52, %53, %54, %55, %56, %57, %58, %59, %60, %61, %62, %63}, "
    "%64, %65, p, 1, 1, 0, 0;\n}\n"
    : "+f"(d[0]), "+f"(d[1]), "+f"(d[2]), "+f"(d[3]), "+f"(d[4]), "+f"(d[5]), "+f"(d[6]), "+f"(d[7]), "+f"(d[8]), "+f"(d[9]), "+f"(d[10]), "+f"(d[11]), "+f"(d[12]), "+f"(d[13]), "+f"(d[14]), "+f"(d[15]), "+f"(d[16]), "+f"(d[17]), "+f"(d[18]), "+f"(d[19]), "+f"(d[20]), "+f"(d[21]), "+f"(d[22]), "+f"(d[23]), "+f"(d[24]), "+f"(d[25]), "+f"(d[26]), "+f"(d[27]), "+f"(d[28]), "+f"(d[29]), "+f"(d[30]), "+f"(d[31]), "+f"(d[32]), "+f"(d[33]), "+f"(d[34]), "+f"(d[35]), "+f"(d[36]), "+f"(d[37]), "+f"(d[38]), "+f"(d[39]), "+f"(d[40]), "+f"(d[41]), "+f"(d[42]), "+f"(d[43]), "+f"(d[44]), "+f"(d[45]), "+f"(d[46]), "+f"(d[47]), "+f"(d[48]), "+f"(d[49]), "+f"(d[50]), "+f"(d[51]), "+f"(d[52]), "+f"(d[53]), "+f"(d[54]), "+f"(d[55]), "+f"(d[56]), "+f"(d[57]), "+f"(d[58]), "+f"(d[59]), "+f"(d[60]), "+f"(d[61]), "+f"(d[62]), "+f"(d[63])
    : "l"(da), "l"(db), "r"(scale_d));
}

__device__ __forceinline__ void wgmma_rs_n128_tb(float (&d)[64], uint32_t a0, uint32_t a1, uint32_t a2, uint32_t a3, uint64_t db, int scale_d) {
  asm volatile("{\n.reg .pred p;\nsetp.ne.b32 p, %69, 0;\n"
    "wgmma.mma_async.sync.aligned.m64n128k16.f32.bf16.bf16 "
    "{%0, %1, %2, %3, %4, %5, %6, %7, %8, %9, %10, %11, %12, %13, %14, %15, %16, %17, %18, %19, %20, %21, %22, %23, %24, %25, %26, %27, %28, %29, %30, %31, %32, %33, %34, %35, %36, %37, %38, %39, %40, %41, %42, %43, %44, %45, %46, %47, %48, %49, %50, %51, %52, %53, %54, %55, %56, %57, %58, %59, %60, %61, %62, %63}, "
    "{%64, %65, %66, %67}, "
    "%68, p, 1, 1, 1;\n}\n"
    : "+f"(d[0]), "+f"(d[1]), "+f"(d[2]), "+f"(d[3]), "+f"(d[4]), "+f"(d[5]), "+f"(d[6]), "+f"(d[7]), "+f"(d[8]), "+f"(d[9]), "+f"(d[10]), "+f"(d[11]), "+f"(d[12]), "+f"(d[13]), "+f"(d[14]), "+f"(d[15]), "+f"(d[16]), "+f"(d[17]), "+f"(d[18]), "+f"(d[19]), "+f"(d[20]), "+f"(d[21]), "+f"(d[22]), "+f"(d[23]), "+f"(d[24]), "+f"(d[25]), "+f"(d[26]), "+f"(d[27]), "+f"(d[28]), "+f"(d[29]), "+f"(d[30]), "+f"(d[31]), "+f"(d[32]), "+f"(d[33]), "+f"(d[34]), "+f"(d[35]), "+f"(d[36]), "+f"(d[37]), "+f"(d[38]), "+f"(d[39]), "+f"(d[40]), "+f"(d[41]), "+f"(d[42]), "+f"(d[43]), "+f"(d[44]), "+f"(d[45]), "+f"(d[46]), "+f"(d[47]), "+f"(d[48]), "+f"(d[49]), "+f"(d[50]), "+f"(d[51]), "+f"(d[52]), "+f"(d[53]), "+f"(d[54]), "+f"(d[55]), "+f"(d[56]), "+f"(d[57]), "+f"(d[58]), "+f"(d[59]), "+f"(d[60]), "+f"(d[61]), "+f"(d[62]), "+f"(d[63])
    : "r"(a0), "r"(a1), "r"(a2), "r"(a3), "l"(db), "r"(scale_d));
}

__host__ __device__ __forceinline__ uint32_t decode_item(int s, int side) {
  int ib = s;
  if (s >= NB0 + SPAN) {
    ib = s - 128;
  } else if (s >= NB0) {
    const int r = s - NB0, na = (r * 128 + SPAN - 1) / SPAN;
    if (((r + 1) * 128 + SPAN - 1) / SPAN != na) return (uint32_t)((na >> 4) << 5 | side << 4 | (na & 15));
    ib = s - na;
  }
  if (ib >= HT * 16) ib = (ib & ~15) | (ib & 3) << 2 | (ib >> 2 & 3);
  return 1024u | (uint32_t)((ib >> 4) << 5 | side << 4 | (ib & 15));
}
__device__ __forceinline__ unsigned launch_epoch() {
  unsigned long long ex;
  asm volatile("ld.relaxed.gpu.global.u64 %0, [%1];" : "=l"(ex) : "l"(&g_ctr.exits) : "memory");
  return (unsigned)(ex / (gridDim.x * 12));
}
__device__ __forceinline__ uint32_t l2_probe(uint32_t off, int cta, int v, int lane) {
  uint8_t* a = reinterpret_cast<uint8_t*>(g_qo) + off + ((cta + v * 9) & 31) * 128 + (cta >> 5) * 16 + v * 4;
  asm volatile("{\n.reg .pred p;\nsetp.eq.u32 p, %1, 0;\n@p st.relaxed.gpu.global.u32 [%0], %1;\n}" ::"l"(a), "r"(lane) : "memory");
  uint32_t best = ~0u;
#pragma unroll
  for (int r = 0; r < 4; r++) {
    uint32_t dt;
    asm volatile("{\n.reg .pred p;\n.reg .u32 v, t0, t1;\n"
                 "setp.eq.u32 p, %2, 0;\nmov.u32 v, 0;\nmov.u32 t1, 0;\n"
                 "mov.u32 t0, %%clock;\n"
                 "@p atom.relaxed.gpu.global.inc.u32 v, [%1], 1000;\n"
                 "setp.ne.u32 p, v, 0xFFFFFFF7;\n"
                 "@p mov.u32 t1, %%clock;\n"
                 "sub.u32 %0, t1, t0;\n}"
                 : "=r"(dt) : "l"(a), "r"(lane) : "memory");
    best = min(best, dt);
  }
  return best;
}
__device__ __forceinline__ int get_role(uint32_t bars) {
  mbar_wait(bars + 648, 0);
  return lds32(bars + 680);
}
__device__ __forceinline__ uint32_t get_phase(uint32_t bars) {
  mbar_wait(bars + 656, 0);
  return lds32(bars + 684);
}
__device__ __forceinline__ void fetch_phase(uint32_t bars, const unsigned* word) {
  uint32_t ph, spins = 0;
  do {
    asm volatile("ld.relaxed.gpu.global.u32 %0, [%1];" : "=r"(ph) : "l"(word) : "memory");
    if (++spins > (1u << 24)) *(volatile int*)nullptr = 0;
  } while ((ph >> 8) != (1u << N_PAGES) - 1);
  sts32(bars + 684, ph);
  mbar_arrive(bars + 656);
}
__device__ __forceinline__ int q_task(const Params& P, int cta, int i, uint32_t bars) {
  if (i == 0) return P.boot[blockIdx.x] >> 8;
  const int role = get_role(bars), side4 = (role >> 4) << 2, r = role & 15;
  if (cta < N_OP) {
    if (i == 1) return P.qorder[wave1(role >> 4) + (r >> 1)] | side4 | (1 + (r & 1)) << 8;
    return (i == 2 && r < 8) ? (XHP + (r & 1)) << 3 | side4 | (r >> 1) : -1;
  }
  const int t = wave1(role >> 4) + N_OP / 4 + r + (i - 1) * QPS;
  return t < P.n_qtiles ? P.qorder[t] | side4 : -1;
}
__device__ __forceinline__ int o_owner(const Params& P, int cta, uint32_t bars) {
  const int role = get_role(bars), side8 = (role >> 4) << 3, r = role & 15;
  if (cta < N_OP) return (r >> 3) << 4 | side8 | (r & 7);
  const int h = (r + QPS - (P.n_qtiles - wave1(role >> 4) - N_OP / 4) % QPS) % QPS;
  return h < 8 ? 16 | side8 | h : -1;
}

__device__ __forceinline__ void feed_last_heads(int w, int quad, uint32_t sbase, unsigned epoch, int cta) {
  static_assert(H0 % 4 == 0, "stage parity");
  const uint32_t bars = sbase + SM_BAR, phase = get_phase(bars);
  const uint64_t pol = pol_ef();
  mbar_wait(bars + 128, 0);
#pragma unroll 1
  for (int h = 0; h < 32 - H0; h++) {
    const uint8_t* src[4];
#pragma unroll
    for (int i = 0; i < 4; i++) src[i] = qo_block(1, H0 + h, quad * 4, w * 4 + i, phase);
    const uint32_t e = bars + 32 + (h & 1) * 16, fb = bars + 80 + (w * 2 + (h & 1)) * 8;
    mbar_wait(e, ((h >> 1) & 1) ^ 1);
    mbar_wait(e + 8, ((h >> 1) & 1) ^ 1);
    const unsigned* c = &g_ctr.cntL[quad * 64 + h * 4 + w];
    for (uint32_t spins = 0;; spins++) {
      unsigned v0, v1;
      asm volatile("ld.relaxed.gpu.global.u32 %0, [%2];\nld.relaxed.gpu.global.u32 %1, [%2+4];"
                   : "=r"(v0), "=r"(v1) : "l"(c) : "memory");
      if ((int)((v0 - epoch - 1) | (v1 - epoch - 1)) >= 0) break;
      if (spins > (1u << 24)) *(volatile int*)nullptr = 0;
    }
    TR(1, 40 + h * 3 + w, 0);
    asm volatile("fence.acquire.gpu;" ::: "memory");
    mbar_expect(fb, 16384);
#pragma unroll
    for (int i = 0; i < 4; i++)
      bulk_g2s_hint(sbase + (h & 1) * 2 * GA_BYTES + w * 16384 + i * 4096, src[i], 4096, fb, pol);
    TR(1, 70 + h * 3 + w, 0);
  }
}

template <bool IS_O, bool HALF>
__device__ __forceinline__ void gemm_mainloop(float (&acc0)[64], float (&acc1)[64], int nk, int keep, uint32_t& it,
                                              uint32_t sbase, int wg, int lane, unsigned* freep) {
  const uint32_t full = sbase + SM_BAR, empty = full + 32;
#pragma unroll 1
  for (int k = 0; k < nk; k++) {
    const uint32_t st = it & 3;
    mbar_wait(full + st * 8, (it >> 2) & 1);
    if (IS_O && HALF && !(k & 1)) mbar_wait(full + 80 + (wg * 2 + ((k >> 1) & 1)) * 8, (k >> 2) & 1);
    if (freep && !(k & 1)) red_relaxed(freep + (k >> 1), 1);
    const uint32_t b = sbase + SM_GB + st * GB_BYTES;
    const uint64_t da = IS_O ? mkdesc(sbase + (st & 2) * GA_BYTES + wg * 16384 + (st & 1) * 1024, 128, 2048, 0)
                             : mkdesc(sbase + st * GA_BYTES + wg * 8192, 16, 1024, 1);
    const uint64_t db = mkdesc(b, 8192, 1024, 1);
    wg_fence();
#pragma unroll
    for (int kk = 0; kk < 4; kk++) {
      wgmma_ss_n128_tb(acc0, da + (IS_O ? kk * 16 : kk * 2), db + kk * 128, (k | kk | keep) != 0);
      if (!HALF) wgmma_ss_n128_tb(acc1, da + (IS_O ? kk * 16 : kk * 2), db + 1024 + kk * 128, (k | kk | keep) != 0);
    }
    wg_commit();
    if (IS_O && HALF) {
      if (k & 1) {
        wg_wait<0>();
        if (lane == 0) { mbar_arrive(empty + st * 8 - 8); mbar_arrive(empty + st * 8); }
      }
    } else if (k > 0) {
      wg_wait<1>();
      if (lane == 0) mbar_arrive(empty + ((it - 1) & 3) * 8);
    }
    it++;
  }
  wg_wait<0>();
  if (!(IS_O && HALF) && lane == 0) mbar_arrive(empty + ((it - 1) & 3) * 8);
  reg_fence(acc0);
  if (!HALF) reg_fence(acc1);
}

__global__ void __launch_bounds__(512, 1) fused_kernel(const __grid_constant__ Params P) {
  extern __shared__ __align__(1024) uint8_t smem_raw[];
  const uint32_t sbase = (s2u(smem_raw) + 1023) & ~1023u;
  const int tid = threadIdx.x, lane = tid & 31;
  const int warp = __shfl_sync(0xffffffffu, tid >> 5, 0), wg = warp >> 2;
  const uint32_t boot = P.boot[blockIdx.x];
  const int cta = boot & 255;
  const bool is_gemm = cta < N_GEMM;
  const uint32_t bars = sbase + SM_BAR;
  const uint32_t first = 1024u | ((cta - N_GEMM) >> 5) << 5 | ((cta - N_GEMM) & 1) << 4 | (((cta - N_GEMM) >> 1) & 15);
  if (tid == 0) {
    TR(7, 0, 0); TCK(2);
  }
  const int n_at = gridDim.x - N_GEMM;
  const int ppage = cta - ((int)gridDim.x - N_PAGES);
  uint32_t poff = 0;
  if (ppage > 0) {
    const uint32_t lo = qo_lo() & ((1u << 21) - 1);
    poff = min((uint32_t)ppage * (1u << 21) - lo, (uint32_t)(N_PAIRS - 1) * 8192u);
  }
  const int nsync = is_gemm ? 512 : 256;
  if (warp == 11) {
    if (elect_one()) {
      if (is_gemm) {
        for (int k = 0; k < 4; k++) mbar_init(bars + k * 8, 2);
      } else {
        mbar_init(bars + 440 + 2 * 8, 1);
        for (int s = 0; s < 4; s++) mbar_init(bars + (2 * KV_SLOTS + s) * 8, 1);
        mbar_init(bars + 4 * 8, 1);
      }
      asm volatile("fence.mbarrier_init.release.cluster;" ::: "memory");
    }
    __syncwarp();
    bar_arrive(0, nsync);
    if (!is_gemm) bar_arrive(12, 320);
    if (lane == 0) TR(7, 11, 0);
    if (elect_one()) {
      if (is_gemm) {
        const int q = boot >> 8, p = (q >> 7) & 1;
        for (int k = 0; k < 4; k++) {
          mbar_expect(bars + k * 8, GA_BYTES);
          tma2(sbase + k * GA_BYTES, &P.xmap[p], bars + k * 8, k * 64, (q & 7) * 192);
          mbar_expect(bars + k * 8, GB_BYTES / 2);
          tma3(sbase + SM_GB + k * GB_BYTES, &P.wqmap[p], bars + k * 8, 0, k * 64, ((q >> 3) & 15) * 4 + ((q >> 8) & 2));
        }
      } else {
        mbar_expect(bars + 440 + 2 * 8, 3 * TILE);
        tma3(sbase + SM_Q, &P.x1map, bars + 440 + 2 * 8, 0, (first & 31) * 48, 0);
        for (int s = 0; s < 4; s++) {
          const uint32_t fb = bars + (2 * KV_SLOTS + s) * 8;
          mbar_expect(fb, KVT);
          tma3(sbase + s * KVT, &P.wq1map, fb, 0, s * 128, ((first >> 5) & 31) * 2);
        }
        mbar_expect(bars + 4 * 8, KVT);
        const int row = ((first & 31) * 32 + ((first >> 5) & 31)) * 512;
        tma3_hint(sbase + 4 * KVT, &P.kmap[1], bars + 4 * 8, 0, row, 0, pol_ef());
      }
    }
    __syncwarp();
    if (lane == 0) TR(7, 10, 0);
    bar_sync(11, 64);
  } else if (warp == 13) {
    if (elect_one()) {
      if (is_gemm) {
        for (int i = 0; i < 4; i++) mbar_init(bars + 32 + i * 8, 12);
        mbar_init(bars + 64, 1);
        mbar_init(bars + 72, 12);
        for (int i = 0; i < 7; i++) mbar_init(bars + 80 + i * 8, 1);
        mbar_init(bars + 640, 2);
      } else {
        for (int i = 0; i < 4 * KV_SLOTS; i++)
          if (i != 4 && (i < 2 * KV_SLOTS || i >= 2 * KV_SLOTS + 4)) mbar_init(bars + i * 8, 1);
        for (int i = 0; i < KV_SLOTS; i++) mbar_init(bars + 352 + i * 8, 12);
        for (int i = 0; i < 2; i++) mbar_init(bars + 440 + i * 8, 1);
        for (int i = 0; i < 3; i++) mbar_init(bars + 464 + i * 8, 4);
        for (int i = 0; i < 4; i++) mbar_init(bars + 488 + i * 8, 1);
        for (int i = 0; i < 3; i++) { mbar_init(bars + 544 + i * 8, 4); mbar_init(bars + 568 + i * 8, 1); }
        mbar_init(bars + 640, 8);
      }
      for (int i = 1; i < 4; i++) mbar_init(bars + 640 + i * 8, 1);
      asm volatile("fence.mbarrier_init.release.cluster;" ::: "memory");
    }
    __syncwarp();
    bar_arrive(11, 64);
    if (!is_gemm) bar_arrive(12, 320);
    bar_sync(0, nsync);
  } else if (!is_gemm && warp < 8) {
    const uint32_t best = l2_probe((wg ? poff : 0) + (warp & 1) * 4096, cta, warp >> 1, lane);
    bar_sync(12, 320);
    if (lane == 0) {
      sts32(bars + 688 + warp * 4, best);
      mbar_arrive(bars + 640);
    }
  } else {
    if (warp == 14 && lane < 13) asm volatile("prefetch.tensormap [%0];" ::"l"(&P.kmap[0] + lane) : "memory");
    bar_sync(0, nsync);
  }

  if (wg == 3) {
    asm volatile("setmaxnreg.dec.sync.aligned.u32 32;");
    const unsigned epoch = warp >= 13 ? launch_epoch() : 0;
    Ctrs::Launch* const L = &g_ctr.launch[epoch & 1];
    if (is_gemm && warp >= 14) {
      const uint32_t best = l2_probe((warp & 1) * 4096, cta, 0, lane);
      if (lane < 4) sts32(bars + 688 + (warp & 1) * 4 + lane * 8, best);
      __syncwarp();
      if (lane == 0) mbar_arrive(bars + 640);
    }
    if (warp == 15) {
      if (elect_one()) {
        if (cta == 0) {
          unsigned* z = reinterpret_cast<unsigned*>(&g_ctr.launch[(epoch & 1) ^ 1]);
          for (int i = 0; i < 10; i++) z[i] = 0;
        }
        mbar_wait(bars + 640, 0);
        uint32_t lo = min(lds32(bars + 688), lds32(bars + 696)), hi = min(lds32(bars + 692), lds32(bars + 700));
        const uint32_t lo2 = min(lds32(bars + 704), lds32(bars + 712)), hi2 = min(lds32(bars + 708), lds32(bars + 716));
        if (ppage <= 0) { lo = min(lo, lo2); hi = min(hi, hi2); }
        TR(7, 8, lo); TR(7, 9, hi);
        const uint32_t side = lo > hi;
        if (ppage >= 0) {
          const uint32_t home = ppage ? side ^ (lo2 > hi2) : 0;
          const uint32_t ph = (home ^ __popc((qo_lo() + poff) & SIDE_BITS)) & 1;
          atomicOr(&L->phase, (ph | 256u) << ppage);
        }
        uint32_t role = side << 4;
        if (is_gemm) {
          const int kind = cta >= N_OP, per = kind ? QPS : N_OP / 2;
          const uint32_t t = atomicAdd(&L->ticket[kind][side], 1u);
          role = t < per ? role | t : (side ^ 1) << 4 | (per - 1 - atomicAdd(&L->ticket[kind][2], 1u));
        }
        sts32(bars + 680, role);
        mbar_arrive(bars + 648);
        TR(7, 5, role);
        if (is_gemm) {
          const int own = o_owner(P, cta, bars);
          if (own >= 16) feed_last_heads(2, (own >> 1) & 7, sbase, epoch, cta);
        } else {
          for (uint32_t n = 0;; n++) {
            mbar_wait(bars + 664, n & 1);
            uint32_t c0, c1;
            asm volatile("ld.relaxed.gpu.global.v2.u32 {%0,%1}, [%2];" : "=r"(c0), "=r"(c1) : "l"(L->item) : "memory");
            uint32_t q = side ^ ((side ? (int)(c1 - c0) : (int)(c0 - c1)) > QLEAD + ((cta * 7) & 31));
            int s = (int)atomicAdd(&L->item[q], 1u) + ((n_at + 1 - (int)q) >> 1);
            if (s >= N_ITEMS) {
              q ^= 1;
              s = (int)atomicAdd(&L->item[q], 1u) + ((n_at + 1 - (int)q) >> 1);
            }
            const uint32_t cap = s >= N_ITEMS - CAP_TAIL / 2 ? CAP_END
                               : (s >= CAP_LO / 2 && s < NB0 + SPAN + CAP_OFF / 2 && cta % CAP_MOD < CAP_NUM) ? 3 : KV_CAP;
            const uint32_t d = s < N_ITEMS ? decode_item(s, q) | cap << 16 : INFO_DONE;
            mbar_wait(bars + 504 + (n & 1) * 8, ((n >> 1) & 1) ^ 1);
            sts32(bars + 536 + (n & 1) * 4, d);
            mbar_arrive(bars + 488 + (n & 1) * 8);
            if (d == INFO_DONE) break;
          }
        }
      }
    } else if (is_gemm) {
      const uint32_t full = bars, empty = bars + 32;
      const bool is_op = cta < N_OP;
      const int kbeg = is_op ? 0 : 2 * H0;
      if (warp == 12) { if (elect_one()) {
        uint32_t it = 4;
        for (int i = 0, q; (q = q_task(P, cta, i, bars)) >= 0; i++) {
          const int mode = q >> 8, p = (q >> 7) & 1, nb = ((q >> 3) & 15) * 4 + (mode & 2);
          for (int k = it & 7; k < 8; k++, it++) {
            const uint32_t st = it & 3, dst = sbase + SM_GB + st * GB_BYTES;
            mbar_wait(empty + st * 8, ((it >> 2) & 1) ^ 1);
            mbar_expect(full + st * 8, mode ? GB_BYTES / 2 : GB_BYTES);
            tma3(dst, &P.wqmap[p], full + st * 8, 0, k * 64, nb);
            if (!mode) tma3(dst + GB_BYTES / 2, &P.wqmap[p], full + st * 8, 0, k * 64, nb + 2);
          }
        }
        const int own = o_owner(P, cta, bars);
        if (own >= 0) {
          const int p = own >> 4, nb = (own & 1) * 4 + (is_op ? 0 : 2);
          for (int k = kbeg; k < 64; k++, it++) {
            const uint32_t st = it & 3, dst = sbase + SM_GB + st * GB_BYTES;
            const bool half = p && k >= 2 * H0;
            mbar_wait(empty + st * 8, ((it >> 2) & 1) ^ 1);
            mbar_expect(full + st * 8, half ? GB_BYTES / 2 : GB_BYTES);
            if (half) mbar_arrive(full + st * 8);
            tma3(dst, &P.womap[p], full + st * 8, 0, k * 64, nb);
            if (!half) tma3(dst + GB_BYTES / 2, &P.womap[p], full + st * 8, 0, k * 64, nb + 2);
          }
        }
      } } else if (warp == 13) {
        uint32_t it = 4;
        for (int i = 0, q; (q = __shfl_sync(0xffffffffu, q_task(P, cta, i, bars), 0)) >= 0; i++) {
          for (int k = it & 7; k < 8; k++, it++) {
            const uint32_t st = it & 3;
            mbar_wait(empty + st * 8, ((it >> 2) & 1) ^ 1);
            if (elect_one()) {
              mbar_expect(full + st * 8, GA_BYTES);
              tma2(sbase + st * GA_BYTES, &P.xmap[(q >> 7) & 1], full + st * 8, k * 64, (q & 7) * 192);
            }
          }
        }
        const int own = __shfl_sync(0xffffffffu, o_owner(P, cta, bars), 0);
        if (own >= 0) {
          const int p = own >> 4, quad = (own >> 1) & 7;
          const unsigned target = (epoch + 1) * 12;
          const uint32_t phase = get_phase(bars);
          const uint64_t pol = pol_ef();
          for (int h = kbeg >> 1; h < (p ? H0 : 32); h++) {
            const uint8_t* blk = qo_block(p, h, quad * 4, lane < 12 ? lane : 0, phase);
            const uint32_t up = __ballot_sync(0xffffffffu, (reinterpret_cast<uintptr_t>(blk) >> 12) & 1);
            const uint8_t* src = reinterpret_cast<const uint8_t*>(g_qo) + qo_pair(p, h, quad * 4, 0) * 8192;
            poll_ge(&g_ctr.cntO[(p * 8 + quad) * 32 + h], target);
            if (lane == 0) TR(1, h, h);
            const uint32_t st = it & 3;
            mbar_wait(empty + st * 8, ((it >> 2) & 1) ^ 1);
            mbar_wait(empty + st * 8 + 8, ((it >> 2) & 1) ^ 1);
            if (elect_one()) {
              mbar_expect(full + st * 8, 2 * GA_BYTES);
              mbar_arrive(full + st * 8 + 8);
#pragma unroll
              for (int i = 0; i < 12; i++)
                bulk_g2s_hint(sbase + st * GA_BYTES + i * 4096, src + (i * 8192 + (((up >> i) & 1) << 12)), 4096, full + st * 8, pol);
            }
            it += 2;
          }
          if (p && elect_one()) {
            mbar_arrive(bars + 128);
            feed_last_heads(0, quad, sbase, epoch, cta);
          }
        }
      } else if (warp == 14) { if (elect_one()) {
        fetch_phase(bars, &L->phase);
        TR(7, 6, 0);
        int n = 0;
        for (int q; (q = q_task(P, cta, n, bars)) >= 0; n++) {
          const int p = (q >> 7) & 1, hp = (q >> 3) & 15, quad = q & 7;
          const int ring = p ? RB : RA;
          if (hp * 2 >= ring) poll_ge(&g_ctr.cntF[(p * 8 + quad) * 32 + hp * 2 + 1 - ring], (epoch + 1) * 2);
          mbar_arrive(bars + 64);
          mbar_wait(bars + 72, n & 1);
          fence_gpu();
          fence_async_global();
          red_relaxed(&g_ctr.cntQ[(p * 8 + quad) * 16 + hp], (q >> 8) ? 1 : 2);
          TR(3, n, q);
        }
        const int own = o_owner(P, cta, bars);
        if (own >= 16) {
          if (is_op) {
            mbar_wait(bars + 72, n & 1);
            fence_gpu();
            red_relaxed(&g_ctr.cntD[own - 16], 1);
          } else {
            poll_ge(&g_ctr.cntD[own - 16], epoch + 1);
            mbar_arrive(bars + 64);
          }
          feed_last_heads(1, (own >> 1) & 7, sbase, epoch, cta);
        }
      } }
    } else {
      if (warp == 12) { if (elect_one()) {
        const uint64_t pol = pol_ef();
        uint32_t d = first | KV_CAP << 16, slot = 0, eph = 0, nb = 0, n = 0;
        uint32_t fph = 15u << (2 * KV_SLOTS) | 16u;
        uint32_t w1 = bars + 4 * 8, w2 = 0, w3 = 0;
        {
          const int row = ((first & 31) * 32 + ((first >> 5) & 31)) * 512;
        for (int t = 1; t <= PF0; t++)
          asm volatile("cp.async.bulk.prefetch.tensor.3d.L2.global [%0, {%1,%2,%3}];"
                       ::"l"(&P.kmap[1] + (BORDER ? t & 2 : (t & 1) * 2)), "r"(0), "r"(row + (BORDER ? t & 1 : t >> 1) * 128), "r"(0) : "memory");
        }
        while (d != INFO_DONE) {
          const uint32_t p = (d >> 10) & 1, cap = d >> 16;
          uint32_t wx = 3 * KV_SLOTS, wy = 3 * KV_SLOTS;
          if (p) {
            wx = nb;
            wy = nb == 2 * KV_SLOTS ? 0 : nb + KV_SLOTS;
            nb = wy == 2 * KV_SLOTS ? 0 : wy + KV_SLOTS;
          }
          const int row = ((d & 31) * (p ? 32 : 8) + ((d >> 5) & 31)) * 512;
          const CUtensorMap* km = &P.kmap[p];
          TR(4, n, d & 2047);
#pragma unroll 1
          for (int t = (n == 0); t < 8; t++) {
            const uint32_t bit = ((t & 1) ? wy : wx) + slot, fb = bars + bit * 8;
            const uint32_t isv = (t >> p) & 1, chunk = p ? (t >> 2) * 2 + (t & 1) : t >> 1;
            const uint32_t ow = cap == 2 ? w2 : cap == 3 ? w3 : 0;
            w3 = w2;
            w2 = w1;
            w1 = fb | ((fph >> bit) & 1);
            fph ^= 1u << bit;
            if (t == REQ_T) mbar_arrive(bars + 664);
            mbar_wait(bars + 352 + slot * 8, eph);
            if (ow) mbar_wait(ow & ~1u, ow & 1);
            mbar_expect(fb, KVT);
            tma3_hint(sbase + slot * KVT, km + isv * 2, fb, 0, row + chunk * 128, 0, pol);
            if (++slot == KV_SLOTS) { slot = 0; eph ^= 1; }
          }
          mbar_wait(bars + 488 + (n & 1) * 8, (n >> 1) & 1);
          d = lds32(bars + 536 + (n & 1) * 4);
          n++;
        }
      } } else if (warp == 13) { if (elect_one()) {
        const unsigned target = (epoch + 1) * 2;
        const uint32_t phase = get_phase(bars);
        uint32_t n = 0, nb = 2, slot0 = (4 + 8) % KV_SLOTS, qph = 0;
        while (true) {
          const uint32_t m = n & 1;
          mbar_wait(bars + 488 + m * 8, (n >> 1) & 1);
          uint32_t d = lds32(bars + 536 + m * 4);
          mbar_arrive(bars + 504 + m * 8);
          n++;
          if (d == INFO_DONE) break;
          d &= 2047;
          TR(3, n * 2, d);
          const int p = d >> 10, hd = (d >> 5) & 31, b = d & 31;
          if (p) {
            poll_ge(&g_ctr.cntQ[(8 + (b >> 2)) * 16 + (hd >> 1)], target);
            TR(3, n * 2 + 1, d);
            for (int r = 0; r < 2; r++) {
              const uint32_t w = nb;
              nb = (nb == 2) ? 0 : nb + 1;
              mbar_wait(bars + 464 + w * 8, (qph >> w) & 1);
              qph ^= 1u << w;
              sts32(bars + 520 + w * 4, d | (((slot0 + r * (2 - BORDER)) % KV_SLOTS) << 11) | (r << 15));
              mbar_expect(bars + 440 + w * 8, QBLK);
              for (int j = 0; j < 3; j++)
                bulk_g2s(sbase + SM_Q + w * TILE + j * 4096, qo_block(1, hd, b, j, phase), 4096, bars + 440 + w * 8);
            }
          } else {
            poll_ge(&g_ctr.cntQ[(b >> 2) * 16 + hd * 2], target);
            poll_ge(&g_ctr.cntQ[(b >> 2) * 16 + hd * 2 + 1], target);
            TR(3, n * 2 + 1, d);
            for (int w = 0; w < 3; w++) {
              mbar_wait(bars + 464 + w * 8, (qph >> w) & 1);
              sts32(bars + 520 + w * 4, d | (slot0 << 11));
              mbar_expect(bars + 440 + w * 8, TILE);
              for (int i = 0; i < 4; i++) {
                const int rb = w * 4 + i;
                bulk_g2s(sbase + SM_Q + w * TILE + i * 4096, qo_block(0, hd * 4 + rb / 3, b, rb % 3, phase), 4096,
                         bars + 440 + w * 8);
              }
            }
            qph ^= 7;
          }
          slot0 = (slot0 + 8) % KV_SLOTS;
        }
        for (int w = 0; w < 3; w++) {
          mbar_wait(bars + 464 + w * 8, (qph >> w) & 1);
          sts32(bars + 520 + w * 4, INFO_DONE);
          mbar_arrive(bars + 440 + w * 8);
        }
      } } else if (warp == 14 && lane == 0) {
        fetch_phase(bars, &L->phase);
        TR(7, 6, 0);
        uint32_t ph = 0, live = 7, spins = 0;
        while (live) {
          uint32_t got = 0, c0[3], c1[3];
#pragma unroll
          for (int w = 0; w < 3; w++) {
            if (!((live >> w) & 1) || !mbar_test(bars + 544 + w * 8, (ph >> w) & 1)) continue;
            ph ^= 1u << w;
            const uint32_t inf = lds32(bars + 592 + w * 4), b = inf & 31, hd = (inf >> 5) & 31;
            mbar_arrive(bars + 568 + w * 8);
            spins = 0;
            if (inf == INFO_DONE) { live &= ~(1u << w); continue; }
            got |= 1u << w;
            c1[w] = 0;
            if (!((inf >> 10) & 1)) {
              c0[w] = ((b >> 2) * 32 + hd * 4 + w) | (3 - w) << 16;
              c1[w] = w + 1;
            } else if (hd >= H0) {
              c0[w] = ((uint32_t)(g_ctr.cntL - g_ctr.cntO) + (b >> 2) * 64 + (hd - H0) * 4 + (b & 3)) | 1 << 16;
            } else {
              c0[w] = ((8 + (b >> 2)) * 32 + hd) | 3 << 16;
            }
            asm volatile("" : "+r"(c0[w]), "+r"(c1[w]));
          }
          if (got) {
            fence_gpu();
            fence_async_global();
#pragma unroll
            for (int w = 0; w < 3; w++) {
              if (!((got >> w) & 1)) continue;
              red_relaxed(g_ctr.cntO + (c0[w] & 65535), c0[w] >> 16);
              if (c1[w]) red_relaxed(g_ctr.cntO + (c0[w] & 65535) + 1, c1[w]);
            }
            continue;
          }
          __nanosleep(20);
          if (++spins > (1u << 26)) break;
        }
      }
    }
  } else {
    const int wq = warp & 3;
    asm volatile("setmaxnreg.inc.sync.aligned.u32 160;");
    if (is_gemm) {
      const bool is_op = cta < N_OP;
      float acc0[64], acc1[64];
      uint32_t it = 0;
#pragma unroll 1
      for (int i = 0, q; (q = __shfl_sync(0xffffffffu, q_task(P, cta, i, bars), 0)) >= 0; i++) {
        const int mode = q >> 8, p = (q >> 7) & 1, h0 = ((q >> 3) & 15) * 2 + (mode >> 1), quad = q & 7;
        if (tid == 0) TR(0, i * 4, q);
        if (mode) gemm_mainloop<false, true>(acc0, acc1, 8, 0, it, sbase, wg, lane, nullptr);
        else gemm_mainloop<false, false>(acc0, acc1, 8, 0, it, sbase, wg, lane, nullptr);
        if (tid == 0) TR(0, i * 4 + 1, q);
        mbar_wait(bars + 64, i & 1);
        if (wg > 0) bar_sync(4 + wg, 256);
        if (tid == 0) TR(0, i * 4 + 2, q);
        const int b = quad * 4 + warp / 3, j = warp % 3;
#pragma unroll
        for (int hh = 0; hh < 2; hh++) {
          const float(&acc)[64] = hh ? acc1 : acc0;
          if (hh && mode) break;
          if (p && (((h0 + hh) * 16 + (b & 15)) << 1 | b >> 4) < n_at) continue;
          uint8_t* dst = qo_block(p, h0 + hh, b, j, get_phase(bars)) + lane * 4;
#pragma unroll
          for (int g = 0; g < 16; g++) {
            *reinterpret_cast<uint32_t*>(dst + g * 128) = pack_bf16(acc[g * 4], acc[g * 4 + 1]);
            *reinterpret_cast<uint32_t*>(dst + 2048 + g * 128) = pack_bf16(acc[g * 4 + 2], acc[g * 4 + 3]);
          }
        }
        if (wg < 2) bar_arrive(5 + wg, 256);
        __syncwarp();
        if (lane == 0) mbar_arrive(bars + 72);
        if (tid == 0) TR(0, i * 4 + 3, q);
      }
      const int own = __shfl_sync(0xffffffffu, o_owner(P, cta, bars), 0);
      if (own >= 0) {
        const int p = own >> 4, quad = (own >> 1) & 7;
        float4* dump = g_dump + (own & 15) * (16 * 384) + tid;
        if (is_op) {
          gemm_mainloop<true, false>(acc0, acc1, p ? 2 * H0 : 64, 0, it, sbase, wg, lane,
                                     tid == 0 ? &g_ctr.cntF[(p * 8 + quad) * 32] : nullptr);
          if (p) {
#pragma unroll
            for (int g = 0; g < 16; g++)
              dump[g * 384] = make_float4(acc1[g * 4], acc1[g * 4 + 1], acc1[g * 4 + 2], acc1[g * 4 + 3]);
            __syncwarp();
            if (lane == 0) mbar_arrive(bars + 72);
          }
        } else {
          mbar_wait(bars + 64, (it >> 3) & 1);
#pragma unroll
          for (int g = 0; g < 16; g++) {
            const float4 v = __ldcg(dump + g * 384);
            acc0[g * 4] = v.x; acc0[g * 4 + 1] = v.y; acc0[g * 4 + 2] = v.z; acc0[g * 4 + 3] = v.w;
          }
        }
        if (tid == 0) TR(2, 1, 0);
        if (p) gemm_mainloop<true, true>(acc0, acc1, 64 - 2 * H0, 1, it, sbase, wg, lane, nullptr);
        if ((tid & 127) == 0) TR(2, wg == 0 ? 0 : 4 + wg, 0);
        const uint32_t r = ((lane >> 3) & 1) * 8 + (lane & 7);
#pragma unroll
        for (int cb = 0; cb < 4; cb++) {
          if (cb == 2 && p) break;
          const float(&acc)[64] = (cb >> 1) ? acc1 : acc0;
          const uint32_t base = sbase + (cb & 2) * GA_BYTES + warp * 4096 + (cb & 1) * 2048 + r * 128;
#pragma unroll
          for (int ks = 0; ks < 4; ks++) {
            const int i = (cb & 1) * 32 + ks * 8;
            asm volatile("stmatrix.sync.aligned.m8n8.x4.shared.b16 [%0], {%1,%2,%3,%4};"
                         ::"r"(base + (((ks * 2 + (lane >> 4)) ^ (lane & 7)) << 4)),
                         "r"(pack_bf16(acc[i], acc[i + 1])), "r"(pack_bf16(acc[i + 2], acc[i + 3])),
                         "r"(pack_bf16(acc[i + 4], acc[i + 5])), "r"(pack_bf16(acc[i + 6], acc[i + 7])) : "memory");
          }
        }
        asm volatile("fence.proxy.async.shared::cta;" ::: "memory");
        __syncwarp();
        if (lane < (p ? 2 : 4)) {
          asm volatile("cp.async.bulk.tensor.2d.global.shared::cta.bulk_group [%0, {%2,%3}], [%1];"
                       ::"l"(&P.omap), "r"(sbase + (lane & 2) * GA_BYTES + warp * 4096 + (lane & 1) * 2048),
                       "r"(p * 512 + (own & 1) * 256 + (is_op ? 0 : 128) + lane * 64), "r"(quad * 192 + warp * 16) : "memory");
          asm volatile("cp.async.bulk.commit_group;" ::: "memory");
          asm volatile("cp.async.bulk.wait_group.read 0;" ::: "memory");
        }
        __syncwarp();
        if ((tid & 127) == 0) TR(2, 8 + wg, 0);
      }
    } else {
      constexpr float SC = 0.08838834764831845f * 1.4426950408889634f, TAU = 8.f;
      uint32_t phq = 0, phd = 1, phk = 0;
      int ntr = 0;
      float o[64], s[64];
      if (wg == 1) bar_arrive(2, 256);
      const int nextw = 2 + (wg + 2) % 3;
      const uint64_t dq = mkdesc(sbase + SM_Q + wg * TILE, 128, 2048, 0);
      if (wg == 2) {
        if (tid == 256) TR(7, 12, 0);
        mbar_wait(bars + 440 + 2 * 8, 0);
        if (tid == 256) TR(7, 13, 0);
        phq = 1;
#pragma unroll 1
        for (int j = 0; j < 4; j++) {
          mbar_wait(bars + (2 * KV_SLOTS + j) * 8, 0);
          const uint64_t da = mkdesc(sbase + SM_Q + j * 12288, 16, 1024, 1), db = mkdesc(sbase + j * KVT, 16384, 1024, 1);
          wg_fence();
#pragma unroll
          for (int kk = 0; kk < 8; kk++)
            wgmma_ss_n128_tb(s, da + (kk >> 2) * 384 + (kk & 3) * 2, db + kk * 128, (j | kk) != 0);
          wg_commit();
          wg_wait<0>();
          if (lane == 0) mbar_arrive_n(bars + 352 + j * 8, 3);
        }
        reg_fence(s);
        phk = 15;
        bar_sync(10, 128);
        if (wq < 3) {
          const uint32_t a = sbase + SM_Q + wq * 4096 + lane * 4;
#pragma unroll
          for (int g = 0; g < 16; g++) {
            const uint32_t v0 = pack_bf16(s[g * 4], s[g * 4 + 1]), v1 = pack_bf16(s[g * 4 + 2], s[g * 4 + 3]);
            sts32(a + g * 128, v0);
            sts32(a + 2048 + g * 128, v1);
            sts32(a + TILE + g * 128, v0);
            sts32(a + TILE + 2048 + g * 128, v1);
          }
          asm volatile("fence.proxy.async.shared::cta;" ::: "memory");
        }
        bar_sync(10, 128);
        if (lane == 0) {
          mbar_arrive(bars + 464 + 2 * 8);
          if (wq < 2) {
            sts32(bars + 520 + wq * 4, first | (wq ? (1u - BORDER) << 11 | 1u << 15 : 4u << 11));
            mbar_arrive(bars + 440 + wq * 8);
          }
        }
      }
#pragma unroll 1
      while (true) {
        mbar_wait(bars + 440 + wg * 8, phq);
        const uint32_t info = __shfl_sync(0xffffffffu, lds32(bars + 520 + wg * 4), 0);
        if (info == INFO_DONE) break;
        if ((tid & 127) == 0) TR(wg, ntr * 3, info & 2047);
        const bool isb = (info >> 10) & 1;
        const uint32_t fbase = bars + (isb ? wg : 3) * (KV_SLOTS * 8);
        const uint32_t sh = isb ? 0 : 16, relcnt = isb ? 3 : 1;
        uint32_t slot = (info >> 11) & 15;
        const bool sender = isb && ((info >> 15) ^ SENDX);
        const int last = isb ? 1 : 3;
        const uint32_t step = isb ? 1 + BORDER : 1;
        const bool active = !(isb && wq == 3);
        float nm0 = 0.f, nm1 = 0.f, l0 = 0.f, l1 = 0.f;

        uint32_t t0;
        bool rdy;
        auto probe = [&]() {
          t0 = slot;
          slot = t0 + step >= KV_SLOTS ? t0 + step - KV_SLOTS : t0 + step;
          rdy = mbar_test(fbase + t0 * 8, (phk >> (sh + t0)) & 1);
        };
        auto take = [&]() {
          if (!rdy) mbar_wait(fbase + t0 * 8, (phk >> (sh + t0)) & 1);
          phk ^= 1u << (sh + t0);
        };
        probe();
#pragma unroll 1
        for (int c = 0; c <= last; c++) {
          take();
          if (c == 0 && (tid & 127) == 0) TR(wg, ntr * 3 + 1, info & 2047);
          {
            const uint64_t d0 = mkdesc(sbase + t0 * KVT, 16, 1024, 1);
            TC(0);
            if (!isb) bar_sync(2 + wg, 256);
            TC(1);
            wg_fence();
#pragma unroll
            for (int ks = 0; ks < 8; ks++) wgmma_ss_n128(s, dq + ks * 16, d0 + (ks >> 2) * 1024 + (ks & 3) * 2, ks != 0);
            wg_commit();
            if (!isb) bar_arrive((wg == 0 && c == 0) ? 3 : nextw, 256);
          }
          {
            const uint32_t e0 = bars + 352 + t0 * 8;
            probe();
            TC(7);
            wg_wait<0>();
            reg_fence(s);
            TC(2);
            if (lane == 0) {
              mbar_arrive_n(e0, relcnt);
              if (c == last) mbar_arrive(bars + 464 + wg * 8);
            }
          }
          uint32_t pr[32];
          {
#pragma unroll
            for (int g = 0; g < 16; g++) {
              s[g * 4] = fmaf(s[g * 4], SC, nm0);
              s[g * 4 + 1] = fmaf(s[g * 4 + 1], SC, nm0);
              s[g * 4 + 2] = fmaf(s[g * 4 + 2], SC, nm1);
              s[g * 4 + 3] = fmaf(s[g * 4 + 3], SC, nm1);
            }
            bool update = c == 0;
            if (!update) {
              int x0 = __float_as_int(s[0]), x1 = __float_as_int(s[1]), x2 = __float_as_int(s[2]), x3 = __float_as_int(s[3]);
#pragma unroll
              for (int g = 4; g < 60; g += 8) {
                x0 = __vimax3_s32(x0, __float_as_int(s[g]), __float_as_int(s[g + 1]));
                x1 = __vimax3_s32(x1, __float_as_int(s[g + 2]), __float_as_int(s[g + 3]));
                x2 = __vimax3_s32(x2, __float_as_int(s[g + 4]), __float_as_int(s[g + 5]));
                x3 = __vimax3_s32(x3, __float_as_int(s[g + 6]), __float_as_int(s[g + 7]));
              }
              x0 = __vimax3_s32(x0, __float_as_int(s[60]), __float_as_int(s[61]));
              x1 = __vimax3_s32(x1, __float_as_int(s[62]), __float_as_int(s[63]));
              update = __any_sync(0xffffffffu, max(__vimax3_s32(x0, x1, x2), x3) > __float_as_int(TAU));
            }
            if (update && active) {
              const float floor = c ? 0.f : -INFINITY;
              float n0 = fmaxf(floor, s[0]), n1 = fmaxf(floor, s[2]), n2 = s[1], n3 = s[3];
#pragma unroll
              for (int g = 1; g < 16; g++) {
                n0 = fmaxf(n0, s[g * 4]);
                n2 = fmaxf(n2, s[g * 4 + 1]);
                n1 = fmaxf(n1, s[g * 4 + 2]);
                n3 = fmaxf(n3, s[g * 4 + 3]);
              }
              n0 = fmaxf(n0, n2);
              n1 = fmaxf(n1, n3);
              n0 = fmaxf(n0, __shfl_xor_sync(0xffffffffu, n0, 1));
              n1 = fmaxf(n1, __shfl_xor_sync(0xffffffffu, n1, 1));
              n0 = fmaxf(n0, __shfl_xor_sync(0xffffffffu, n0, 2));
              n1 = fmaxf(n1, __shfl_xor_sync(0xffffffffu, n1, 2));
              nm0 -= n0;
              nm1 -= n1;
#pragma unroll
              for (int g = 0; g < 16; g++) {
                s[g * 4] -= n0;
                s[g * 4 + 1] -= n0;
                s[g * 4 + 2] -= n1;
                s[g * 4 + 3] -= n1;
              }
              if (c) {
                const float a0 = ex2(-n0), a1 = ex2(-n1);
                l0 *= a0;
                l1 *= a1;
#pragma unroll
                for (int g = 0; g < 16; g++) {
                  o[g * 4] *= a0;
                  o[g * 4 + 1] *= a0;
                  o[g * 4 + 2] *= a1;
                  o[g * 4 + 3] *= a1;
                }
              }
            }
          }
          auto exp_part = [&](int g0, int g1) {
#pragma unroll
            for (int g = g0; g < g1; g++) {
              const float e0 = ex2(s[g * 4]), e1 = ex2(s[g * 4 + 1]), e2 = ex2(s[g * 4 + 2]), e3 = ex2(s[g * 4 + 3]);
              l0 += e0 + e1;
              l1 += e2 + e3;
              pr[g * 2] = pack_bf16(e0, e1);
              pr[g * 2 + 1] = pack_bf16(e2, e3);
            }
          };
          exp_part(0, 2 * SPLIT);
          TC(3);
          take();
          TC(4);
          {
            const uint64_t d0 = mkdesc(sbase + t0 * KVT, 16384, 1024, 1);
            const bool turn = !isb && !(wg == 2 && c == 3);
            if (turn) bar_sync(2 + wg, 256);
            TC(5);
            wg_fence();
#pragma unroll
            for (int kk = 0; kk < SPLIT; kk++)
              wgmma_rs_n128_tb(o, pr[kk * 4], pr[kk * 4 + 1], pr[kk * 4 + 2], pr[kk * 4 + 3], d0 + kk * 128, (kk | c) != 0);
            wg_commit();
            if (turn) bar_arrive(nextw, 256);
          }
          exp_part(2 * SPLIT, 16);
          {
            const uint64_t d1 = mkdesc(sbase + t0 * KVT, 16384, 1024, 1);
            wg_fence();
#pragma unroll
            for (int kk = SPLIT; kk < 8; kk++)
              wgmma_rs_n128_tb(o, pr[kk * 4], pr[kk * 4 + 1], pr[kk * 4 + 2], pr[kk * 4 + 3], d1 + kk * 128, 1);
            wg_commit();
            const uint32_t e0 = bars + 352 + t0 * 8;
            if (c < last) {
              if (!BORDER && isb) slot = (slot >= KV_SLOTS - 2) ? slot + 2 - KV_SLOTS : slot + 2;
              probe();
            } else {
              l0 += __shfl_xor_sync(0xffffffffu, l0, 1);
              l1 += __shfl_xor_sync(0xffffffffu, l1, 1);
              l0 += __shfl_xor_sync(0xffffffffu, l0, 2);
              l1 += __shfl_xor_sync(0xffffffffu, l1, 2);
            }
            wg_wait<0>();
            reg_fence(o);
            TC(6);
            if (lane == 0 && !(sender && c == last)) {
              mbar_arrive_n(e0, relcnt);
            }
          }
        }
        phq ^= 1;
        if (sender) {
          { const int c = 2; (void)c; TC(0); }
          bar_sync(8 + wg, 128);
          if (active) {
            const uint32_t a0 = sbase + t0 * KVT + (tid & 127) * 16;
#pragma unroll
            for (int g = 0; g < 16; g++)
              asm volatile("st.shared.v4.f32 [%0], {%1,%2,%3,%4};" ::"r"(a0 + g * 2048),
                           "f"(o[g * 4]), "f"(o[g * 4 + 1]), "f"(o[g * 4 + 2]), "f"(o[g * 4 + 3]) : "memory");
            asm volatile("st.shared.v4.f32 [%0], {%1,%2,%3,%4};" ::"r"(sbase + t0 * KVT + wq * 2048 + 1536 + lane * 16),
                         "f"(nm0), "f"(nm1), "f"(l0), "f"(l1) : "memory");
            asm volatile("fence.proxy.async.shared::cta;" ::: "memory");
          }
          bar_arrive(5 + wg, 256);
          { const int c = 2; (void)c; TC(1); }
          if ((tid & 127) == 0) TR(wg, ntr * 3 + 2, info & 2047);
          ntr++;
          continue;
        }
        const int hd = (info >> 5) & 31;
        uint8_t* dst = qo_block(isb, isb ? hd : hd * 4 + warp / 3, info & 31, isb ? wq : warp % 3, get_phase(bars)) + lane * 4;
        mbar_wait(bars + 568 + wg * 8, phd);
        if ((tid & 127) == 0) sts32(bars + 592 + wg * 4, info);
        if (isb) {
          const uint32_t x0 = (t0 + (SENDX ? KV_SLOTS - 2 + BORDER : 2 - BORDER)) % KV_SLOTS;
          bar_sync(5 + (wg + 1 + SENDX) % 3, 256);
          if (active) {
            const uint32_t a0 = sbase + x0 * KVT + (tid & 127) * 16;
            float pm0, pm1, pl0, pl1;
            asm volatile("ld.shared.v4.f32 {%0,%1,%2,%3}, [%4];" : "=f"(pm0), "=f"(pm1), "=f"(pl0), "=f"(pl1)
                         : "r"(sbase + x0 * KVT + wq * 2048 + 1536 + lane * 16) : "memory");
#pragma unroll
            for (int g = 0; g < 16; g++)
              asm volatile("ld.shared.v4.f32 {%0,%1,%2,%3}, [%4];"
                           : "=f"(s[g * 4]), "=f"(s[g * 4 + 1]), "=f"(s[g * 4 + 2]), "=f"(s[g * 4 + 3])
                           : "r"(a0 + g * 2048) : "memory");
            { const int c = 2; (void)c; TC(2); }
            __syncwarp();
            if (lane == 0) mbar_arrive_n(bars + 352 + x0 * 8, 4);
            const float n0 = fminf(nm0, pm0), n1 = fminf(nm1, pm1);
            float a0s = ex2(n0 - nm0), a1s = ex2(n1 - nm1), p0s = ex2(n0 - pm0), p1s = ex2(n1 - pm1);
            const float i0 = 1.f / (l0 * a0s + pl0 * p0s), i1 = 1.f / (l1 * a1s + pl1 * p1s);
            a0s *= i0; p0s *= i0; a1s *= i1; p1s *= i1;
#pragma unroll
            for (int g = 0; g < 16; g++) {
              uint8_t* d2 = dst + g * 128;
              *reinterpret_cast<uint32_t*>(d2) =
                  pack_bf16(fmaf(o[g * 4], a0s, s[g * 4] * p0s), fmaf(o[g * 4 + 1], a0s, s[g * 4 + 1] * p0s));
              *reinterpret_cast<uint32_t*>(d2 + 2048) =
                  pack_bf16(fmaf(o[g * 4 + 2], a1s, s[g * 4 + 2] * p1s), fmaf(o[g * 4 + 3], a1s, s[g * 4 + 3] * p1s));
            }
          }
          { const int c = 2; (void)c; TC(3); }
        } else {
          const float i0 = 1.f / l0, i1 = 1.f / l1;
#pragma unroll
          for (int g = 0; g < 16; g++) {
            uint8_t* d2 = dst + g * 128;
            *reinterpret_cast<uint32_t*>(d2) = pack_bf16(o[g * 4] * i0, o[g * 4 + 1] * i0);
            *reinterpret_cast<uint32_t*>(d2 + 2048) = pack_bf16(o[g * 4 + 2] * i1, o[g * 4 + 3] * i1);
          }
        }
        __syncwarp();
        if (lane == 0) mbar_arrive(bars + 544 + wg * 8);
        phd ^= 1;
        if ((tid & 127) == 0) TR(wg, ntr * 3 + 2, info & 2047);
        ntr++;
      }
      mbar_wait(bars + 568 + wg * 8, phd);
      if ((tid & 127) == 0) sts32(bars + 592 + wg * 4, INFO_DONE);
      __syncwarp();
      if (lane == 0) mbar_arrive(bars + 544 + wg * 8);
    }
    if (lane == 0) asm volatile("red.relaxed.gpu.global.add.u64 [%0], 1;" ::"l"(&g_ctr.exits) : "memory");
  }
}

typedef CUresult (*EncFn)(CUtensorMap*, CUtensorMapDataType, cuuint32_t, void*, const cuuint64_t*, const cuuint64_t*,
                          const cuuint32_t*, const cuuint32_t*, CUtensorMapInterleave, CUtensorMapSwizzle,
                          CUtensorMapL2promotion, CUtensorMapFloatOOBfill);

#define PROMO_KV CU_TENSOR_MAP_L2_PROMOTION_L2_256B
#define PROMO_W CU_TENSOR_MAP_L2_PROMOTION_L2_128B
void enc(EncFn fn, CUtensorMap* m, const void* base, int rank, const cuuint64_t* dims, const cuuint64_t* strides,
         const cuuint32_t* box, CUtensorMapL2promotion promo = PROMO_W) {
  cuuint32_t es[3] = {1, 1, 1};
  fn(m, CU_TENSOR_MAP_DATA_TYPE_BFLOAT16, rank, const_cast<void*>(base), dims, strides, box, es,
     CU_TENSOR_MAP_INTERLEAVE_NONE, CU_TENSOR_MAP_SWIZZLE_128B, promo,
     CU_TENSOR_MAP_FLOAT_OOB_FILL_NONE);
}

}

extern "C" void kernel_launch(void* const* d_in, const int* in_sizes, int n_in, void* d_out, int out_size) {
  (void)in_sizes; (void)n_in; (void)out_size;
  static EncFn fn = nullptr;
  static int n_sm = 0;
  if (!fn) {
    void* f = nullptr;
    cudaDriverEntryPointQueryResult qr;
    cudaGetDriverEntryPoint("cuTensorMapEncodeTiled", &f, cudaEnableDefault, &qr);
    fn = (EncFn)f;
    int dev = 0;
    cudaGetDevice(&dev);
    cudaDeviceGetAttribute(&n_sm, cudaDevAttrMultiProcessorCount, dev);
    cudaFuncSetAttribute(fused_kernel, cudaFuncAttributeMaxDynamicSharedMemorySize, SMEM_BYTES);
  }
  Params P;
  for (int p = 0; p < 2; p++) {
    const void* x = d_in[p * 5 + 0];
    const void* k = d_in[p * 5 + 1];
    const void* v = d_in[p * 5 + 2];
    const void* wq = d_in[p * 5 + 3];
    const void* wo = d_in[p * 5 + 4];
    {
      cuuint64_t dims[3] = {64, (cuuint64_t)(p ? 32 : 8) * 32 * 512, 2}, str[2] = {256, 128};
      cuuint32_t box[3] = {64, 128, 2};
      enc(fn, &P.kmap[p], k, 3, dims, str, box, PROMO_KV);
      enc(fn, &P.vmap[p], v, 3, dims, str, box, PROMO_KV);
    }
    {
      cuuint64_t dims[2] = {512, 1536}, str[1] = {1024};
      cuuint32_t box[2] = {64, 192};
      enc(fn, &P.xmap[p], x, 2, dims, str, box);
    }
    {
      cuuint64_t dims[3] = {64, 512, 64}, str[2] = {8192, 128};
      cuuint32_t box[3] = {64, 64, 2};
      enc(fn, &P.wqmap[p], wq, 3, dims, str, box);
    }
    {
      cuuint64_t dims[3] = {64, 4096, 8}, str[2] = {1024, 128};
      cuuint32_t box[3] = {64, 64, 2};
      enc(fn, &P.womap[p], wo, 3, dims, str, box);
    }
  }
  {
    cuuint64_t dims[3] = {64, 1536, 8}, str[2] = {1024, 128};
    cuuint32_t box[3] = {64, 48, 8};
    enc(fn, &P.x1map, d_in[5], 3, dims, str, box);
  }
  {
    cuuint64_t dims[3] = {64, 512, 64}, str[2] = {8192, 128};
    cuuint32_t box[3] = {64, 128, 2};
    enc(fn, &P.wq1map, d_in[8], 3, dims, str, box);
  }
  {
    cuuint64_t dims[2] = {1024, 1536}, str[1] = {2048};
    cuuint32_t box[2] = {64, 16};
    enc(fn, &P.omap, d_out, 2, dims, str, box);
  }
  {
    bool seen[256] = {};
    int n = 0;
    for (int s = (n_sm - N_GEMM) / 2; s < N_ITEMS; s++) {
      const uint32_t d = decode_item(s, 0);
      const int p = d >> 10, hd = (d >> 5) & 31, quad = (d & 31) >> 2;
      for (int e = 0; e < (p ? 1 : 2); e++) {
        const int id = (p << 7) | ((p ? hd >> 1 : hd * 2 + e) << 3) | quad;
        if (!p && hd == XHP / 2) continue;
        if (!seen[id]) { seen[id] = true; P.qorder[n++] = (uint8_t)id; }
      }
    }
    P.n_qtiles = n;
  }
  for (int bi = 0; bi < n_sm; bi++) {
    const int g = bi * N_GEMM / n_sm, q = g * N_QP / N_GEMM;
    const int c = (bi + 1) * N_GEMM / n_sm == g ? N_GEMM + bi - g : (g + 1) * N_QP / N_GEMM != q ? N_OP + q : g - q;
    P.boot[bi] = c | (c < N_GEMM ? (P.qorder[c >> 2] | (c & 2) << 1 | (1 + (c & 1)) << 8) << 8 : 0);
  }
  fused_kernel<<<n_sm, 512, SMEM_BYTES>>>(P);
}
```
